```python
import torch

def _softmax(x, axis=-1):
    return torch.softmax(x, dim=axis)

def _gelu(x):
    return torch.nn.functional.gelu(x, approximate='tanh')

def _silu(x):
    return torch.nn.functional.silu(x)

def _sigmoid(x):
    return torch.sigmoid(x)

def _layernorm(x, axis=-1, eps=1e-05):
    m = x.mean(dim=axis, keepdim=True)
    v = x.var(dim=axis, keepdim=True, unbiased=False)
    return (x - m) / torch.sqrt(v + eps)

def _scatter_add(tgt, idx, src, axis=0):
    return tgt.clone().index_add_(axis, idx, src)

def _segment_sum(src, seg, n):
    out = torch.zeros((n,) + src.shape[1:], dtype=src.dtype)
    return out.index_add_(0, seg, src)

def _pad(x, pw):
    flat = tuple((v for pair in reversed(pw) for v in pair))
    return torch.nn.functional.pad(x, flat)
kernel_name = 'adaLN_cond__mha_block_cached__dense_activation_silu__prompt'

def setup_inputs():

    _w = lambda a: (lambda t: t.to(torch.bfloat16) if t.is_floating_point() else t)(torch.as_tensor(a))

    def _A_setup():
        B, Sq, D = (1, 2048, 448)
        H, Sk, Dh = (16, 2048, 256)
        return {'x': _w((lambda *s: torch.randn(*s, dtype=torch.bfloat16) * 0.1)(B, Sq, D)), 'k_cache': _w((lambda *s: torch.randn(*s, dtype=torch.bfloat16) * 0.8)(B, H, Sk, Dh)), 'v_cache': _w((lambda *s: torch.randn(*s, dtype=torch.bfloat16) * 3.2)(B, H, Sk, Dh)), 'wq': _w((lambda *s: torch.randn(*s, dtype=torch.bfloat16) * 0.8)(D, H * Dh) * D ** (-0.5)), 'wo': _w((lambda *s: torch.randn(*s, dtype=torch.bfloat16) * 3.2)(H * Dh, D) * (H * Dh) ** (-0.5))}
    _A_in = _A_setup()

    def _B_setup():
        B, S, D, F = (1, 2048, 448, 1792)
        return {'x': _w((lambda *s: torch.randn(*s, dtype=torch.bfloat16) * 0.1)(B, S, D)), 'w1': _w((lambda *s: torch.randn(*s, dtype=torch.bfloat16) * 3.2)(D, F) * D ** (-0.5)), 'w2': _w((lambda *s: torch.randn(*s, dtype=torch.bfloat16) * 3.2)(F, D) * F ** (-0.5))}
    _B_in = _B_setup()
    return {'A_x': _A_in['x'], 'A_k_cache': _A_in['k_cache'], 'A_v_cache': _A_in['v_cache'], 'A_wq': _A_in['wq'], 'A_wo': _A_in['wo'], 'B_x': _B_in['x'], 'B_w1': _B_in['w1'], 'B_w2': _B_in['w2'], 'c': _w((lambda *s: torch.randn(*s, dtype=torch.bfloat16) * 0.1)(1, 448) * 8.0), 'w_mod': _w((lambda *s: torch.randn(*s, dtype=torch.bfloat16) * 0.1)(448, 6 * 448) * 448 ** (-0.5) * 8.0)}

def reference(A_x, A_k_cache, A_v_cache, A_wq, A_wo, B_x, B_w1, B_w2, c, w_mod):

    def _A_ref(x, k_cache, v_cache, wq, wo):
        B, Sq, D = x.shape
        H, Dh = (16, 256)
        q = (lambda x, *d: x.permute(*d))((x @ wq).reshape(B, Sq, H, Dh), 0, 2, 1, 3)
        scores = torch.einsum('bhqd,bhkd->bhqk', q, k_cache) * Dh ** (-0.5)
        p = _softmax(scores, axis=-1)
        o = torch.einsum('bhqk,bhkd->bhqd', p, v_cache)
        return (lambda x, *d: x.permute(*d))(o, 0, 2, 1, 3).reshape(B, Sq, H * Dh) @ wo

    def _B_ref(x, w1, w2):
        h = torch.einsum('bsd,df->bsf', x, w1)
        h = _silu(h)
        out = torch.einsum('bsf,fd->bsd', h, w2)
        return out
    x = A_x
    mod = (_silu(c) @ w_mod).reshape(c.shape[0], 6, 1, -1)
    sa, ca, ga, sb, cb, gb = (mod[:, 0].clone(), mod[:, 1].clone(), mod[:, 2].clone(), mod[:, 3].clone(), mod[:, 4].clone(), mod[:, 5].clone())
    h = _layernorm(x, axis=-1) * (1 + ca) + sa
    x = x + ga * _A_ref(h, A_k_cache, A_v_cache, A_wq, A_wo)
    h = _layernorm(x, axis=-1) * (1 + cb) + sb
    x = x + gb * _B_ref(h, B_w1, B_w2)
    return x
```

```cpp
#include <cuda_runtime.h>
#include <cuda.h>
#include <cuda_bf16.h>
#include <stdint.h>

namespace {

typedef __nv_bfloat16 bf16;

constexpr int SEQ = 2048, DM = 448, NH = 16, HD = 256, FF = 1792;
constexpr int NSLOT = 5;
constexpr int SLOT = 32768;
constexpr int SM_Q = 0;
constexpr int SM_RING = 65536;
constexpr int SM_BAR = SM_RING + NSLOT * SLOT;
constexpr int SM_MOD0 = SM_BAR + 144;
constexpr int SM_TOTAL = SM_MOD0 + 1792;
constexpr int SM_GV = SM_RING + SLOT + 16384;
constexpr int SM_GC = SM_GV + 14336;
constexpr int SM_LAUNCH = SM_TOTAL;

constexpr int FL_MOD = 0, FL_EPOCH = 2, FL_H = 3, FL_G1 = 19, FL_G2 = 35, FL_COUNT = 51;

constexpr int NUM_MAPS = 14;
struct alignas(64) Params {
  CUtensorMap tmK, tmV, tmWQ, tmH, tmO1, tmWO, tmOut, tmX1, tmW1, tmW2, tmX, tmWMu, tmWMn, tmH16;
  const bf16* x; const bf16* c; const bf16* wmod; bf16* out;
  uint32_t zero;
};

__device__ __align__(1024) bf16 g_h[SEQ * DM];
__device__ __align__(1024) bf16 g_o1[8 * SEQ * HD];
struct SmallBufs {
  unsigned flags[FL_COUNT * 32];
  uint32_t modt[8 * 2 * DM];
  bf16 mod[6 * DM];
};
__device__ __align__(32768) SmallBufs g_small;
#define g_flags (g_small.flags)
#define g_modt (g_small.modt)
#define g_mod (g_small.mod)

#define WATCHDOG_SPINS 0x400000u

__device__ __forceinline__ uint32_t smem_u32(const void* p) { return (uint32_t)__cvta_generic_to_shared(p); }
__device__ __forceinline__ void mbar_init(uint32_t bar, uint32_t cnt) { asm volatile("mbarrier.init.shared::cta.b64 [%0], %1;" :: "r"(bar), "r"(cnt)); }
__device__ __forceinline__ void mbar_expect_tx(uint32_t bar, uint32_t bytes) { asm volatile("mbarrier.arrive.expect_tx.shared::cta.b64 _, [%0], %1;" :: "r"(bar), "r"(bytes) : "memory"); }
__device__ __forceinline__ void mbar_arrive(uint32_t bar) { asm volatile("mbarrier.arrive.shared::cta.b64 _, [%0];" :: "r"(bar) : "memory"); }
__device__ __forceinline__ void mbar_wait(uint32_t bar, uint32_t parity) {
  asm volatile("{\n.reg .pred p;\n.reg .u32 c;\nmov.u32 c, 0;\nWAIT_LOOP:\n"
               "mbarrier.try_wait.parity.shared::cta.b64 p, [%0], %1;\n@p bra DONE;\n"
               "add.u32 c, c, 1;\nsetp.lt.u32 p, c, %2;\n@p bra WAIT_LOOP;\ntrap;\nDONE:\n}"
               :: "r"(bar), "r"(parity), "n"(WATCHDOG_SPINS) : "memory");
}
__device__ __forceinline__ bool mbar_test(uint32_t bar, uint32_t parity) {
  uint32_t ok;
  asm volatile("{\n.reg .pred p;\nmbarrier.test_wait.parity.shared::cta.b64 p, [%1], %2;\nselp.u32 %0, 1, 0, p;\n}" : "=r"(ok) : "r"(bar), "r"(parity) : "memory");
  return ok != 0;
}
__device__ __forceinline__ void mbar_arrive_cluster(uint32_t bar, uint32_t cta) {
  asm volatile("{\n.reg .b32 ra;\nmapa.shared::cluster.u32 ra, %0, %1;\nmbarrier.arrive.shared::cluster.b64 _, [ra];\n}" :: "r"(bar), "r"(cta) : "memory");
}
__device__ __forceinline__ uint32_t cluster_rank() { uint32_t r; asm volatile("mov.u32 %0, %%cluster_ctarank;" : "=r"(r)); return r; }
__device__ __forceinline__ void cluster_arrive() { asm volatile("barrier.cluster.arrive.relaxed.aligned;" ::: "memory"); }
__device__ __forceinline__ void cluster_wait() { asm volatile("barrier.cluster.wait.acquire.aligned;" ::: "memory"); }
__device__ __forceinline__ void wg_fence() { asm volatile("wgmma.fence.sync.aligned;" ::: "memory"); }
__device__ __forceinline__ void wg_commit() { asm volatile("wgmma.commit_group.sync.aligned;" ::: "memory"); }
template<int N> __device__ __forceinline__ void wg_wait() { asm volatile("wgmma.wait_group.sync.aligned %0;" :: "n"(N) : "memory"); }
template<int N> __device__ __forceinline__ void reg_fence(float (&d)[N]) {
  #pragma unroll
  for (int i = 0; i < N; i++) asm volatile("" : "+f"(d[i]) :: "memory");
}
__device__ __forceinline__ uint32_t pack_bf16(float lo, float hi) { uint32_t r; asm("cvt.rn.bf16x2.f32 %0, %1, %2;" : "=r"(r) : "f"(hi), "f"(lo)); return r; }
__device__ __forceinline__ float bf_lo(uint32_t v) { return __uint_as_float(v << 16); }
__device__ __forceinline__ float bf_hi(uint32_t v) { return __uint_as_float(v & 0xffff0000u); }
__device__ __forceinline__ uint32_t bf2_fma(uint32_t a, uint32_t b, uint32_t c) { uint32_t d; asm("fma.rn.bf16x2 %0, %1, %2, %3;" : "=r"(d) : "r"(a), "r"(b), "r"(c)); return d; }
__device__ __forceinline__ uint32_t bf2_add(uint32_t a, uint32_t b) { uint32_t d; asm("add.rn.bf16x2 %0, %1, %2;" : "=r"(d) : "r"(a), "r"(b)); return d; }
__device__ __forceinline__ void mma16816(float (&d)[4], uint32_t a0, uint32_t a1, uint32_t a2, uint32_t a3, uint32_t b0, uint32_t b1) {
  asm volatile("mma.sync.aligned.m16n8k16.row.col.f32.bf16.bf16.f32 {%0,%1,%2,%3}, {%4,%5,%6,%7}, {%8,%9}, {%0,%1,%2,%3};"
    : "+f"(d[0]), "+f"(d[1]), "+f"(d[2]), "+f"(d[3]) : "r"(a0), "r"(a1), "r"(a2), "r"(a3), "r"(b0), "r"(b1));
}
__device__ __forceinline__ float ex2(float x) { float y; asm("ex2.approx.ftz.f32 %0, %1;" : "=f"(y) : "f"(x)); return y; }
__device__ __forceinline__ float rcp(float x) { float y; asm("rcp.approx.ftz.f32 %0, %1;" : "=f"(y) : "f"(x)); return y; }
__device__ __forceinline__ float silu_f(float x) { return x * rcp(1.f + ex2(-1.4426950408889634f * x)); }
__device__ __forceinline__ float tanh_f(float x) { float y; asm("tanh.approx.f32 %0, %1;" : "=f"(y) : "f"(x)); return y; }
__device__ __forceinline__ uint32_t silu2_pack(float x, float y) {
  const float hx = 0.5f * x, hy = 0.5f * y;
  return pack_bf16(fmaf(hx, tanh_f(hx), hx), fmaf(hy, tanh_f(hy), hy));
}
constexpr uint32_t HI_SW128 = (1024u >> 4) | (1u << 30);
__device__ __forceinline__ uint32_t desc_lo(uint32_t addr, uint32_t lbo_bytes) { return ((addr & 0x3FFFF) >> 4) | ((lbo_bytes >> 4) << 16); }
__device__ __forceinline__ uint64_t mk_desc(uint32_t lo, uint32_t hi) { uint64_t d; asm("mov.b64 %0, {%1, %2};" : "=l"(d) : "r"(lo), "r"(hi)); return d; }
__device__ __forceinline__ void named_sync(int id, int n) { asm volatile("bar.sync %0, %1;" :: "r"(id), "r"(n) : "memory"); }
__device__ __forceinline__ void named_arrive(int id, int n) { asm volatile("bar.arrive %0, %1;" :: "r"(id), "r"(n) : "memory"); }
__device__ __forceinline__ void fence_async_smem() { asm volatile("fence.proxy.async.shared::cta;" ::: "memory"); }
__device__ __forceinline__ void fence_async_global() { asm volatile("fence.proxy.async.global;" ::: "memory"); }
__device__ __forceinline__ void ldsm_x4(uint32_t& r0, uint32_t& r1, uint32_t& r2, uint32_t& r3, uint32_t addr) {
  asm volatile("ldmatrix.sync.aligned.m8n8.x4.shared.b16 {%0, %1, %2, %3}, [%4];" : "=r"(r0), "=r"(r1), "=r"(r2), "=r"(r3) : "r"(addr) : "memory");
}
__device__ __forceinline__ void stsm_x4(uint32_t addr, uint32_t r0, uint32_t r1, uint32_t r2, uint32_t r3) {
  asm volatile("stmatrix.sync.aligned.m8n8.x4.shared.b16 [%0], {%1, %2, %3, %4};" :: "r"(addr), "r"(r0), "r"(r1), "r"(r2), "r"(r3) : "memory");
}
__device__ __forceinline__ void tma_load_2d(uint32_t dst, const CUtensorMap* tm, uint32_t bar, int c0, int c1) {
  asm volatile("cp.async.bulk.tensor.2d.shared::cluster.global.mbarrier::complete_tx::bytes [%0], [%1, {%3, %4}], [%2];"
    :: "r"(dst), "l"(tm), "r"(bar), "r"(c0), "r"(c1) : "memory");
}
__device__ __forceinline__ void tma_load_2d_mc(uint32_t dst, const CUtensorMap* tm, uint32_t bar, int c0, int c1) {
  asm volatile("cp.async.bulk.tensor.2d.shared::cluster.global.mbarrier::complete_tx::bytes.multicast::cluster [%0], [%1, {%3, %4}], [%2], %5;"
    :: "r"(dst), "l"(tm), "r"(bar), "r"(c0), "r"(c1), "h"((uint16_t)3) : "memory");
}
__device__ __forceinline__ void tma_load_3d_mc(uint32_t dst, const CUtensorMap* tm, uint32_t bar, int c0, int c1, int c2) {
  asm volatile("cp.async.bulk.tensor.3d.shared::cluster.global.mbarrier::complete_tx::bytes.multicast::cluster [%0], [%1, {%3, %4, %5}], [%2], %6;"
    :: "r"(dst), "l"(tm), "r"(bar), "r"(c0), "r"(c1), "r"(c2), "h"((uint16_t)3) : "memory");
}
__device__ __forceinline__ void bulk_load(uint32_t dst, const void* src, uint32_t bytes, uint32_t bar) {
  asm volatile("cp.async.bulk.shared::cluster.global.mbarrier::complete_tx::bytes [%0], [%1], %2, [%3];"
    :: "r"(dst), "l"(src), "r"(bytes), "r"(bar) : "memory");
}
__device__ __forceinline__ void tma_prefetch_2d(const CUtensorMap* tm, int c0, int c1) {
  asm volatile("cp.async.bulk.prefetch.tensor.2d.L2.global [%0, {%1, %2}];" :: "l"(tm), "r"(c0), "r"(c1) : "memory");
}
__device__ __forceinline__ void tma_prefetch_3d(const CUtensorMap* tm, int c0, int c1, int c2) {
  asm volatile("cp.async.bulk.prefetch.tensor.3d.L2.global [%0, {%1, %2, %3}];" :: "l"(tm), "r"(c0), "r"(c1), "r"(c2) : "memory");
}
__device__ __forceinline__ void tma_store_2d(const CUtensorMap* tm, uint32_t src, int c0, int c1) {
  asm volatile("cp.async.bulk.tensor.2d.global.shared::cta.bulk_group [%0, {%2, %3}], [%1];"
    :: "l"(tm), "r"(src), "r"(c0), "r"(c1) : "memory");
}
__device__ __forceinline__ void tma_reduce_add_2d(const CUtensorMap* tm, uint32_t src, int c0, int c1) {
  asm volatile("cp.reduce.async.bulk.tensor.2d.global.shared::cta.add.tile.bulk_group [%0, {%2, %3}], [%1];"
    :: "l"(tm), "r"(src), "r"(c0), "r"(c1) : "memory");
}
__device__ __forceinline__ void bulk_commit() { asm volatile("cp.async.bulk.commit_group;" ::: "memory"); }
template<int N> __device__ __forceinline__ void bulk_wait_read() { asm volatile("cp.async.bulk.wait_group.read %0;" :: "n"(N) : "memory"); }
template<int N> __device__ __forceinline__ void bulk_wait() { asm volatile("cp.async.bulk.wait_group %0;" :: "n"(N) : "memory"); }
__device__ __forceinline__ void flag_signal(int idx) {
  asm volatile("red.release.gpu.global.add.u32 [%0], 1;" :: "l"(g_flags + idx * 32) : "memory");
}
__device__ __forceinline__ void flag_signal_relaxed(int idx) {
  asm volatile("red.relaxed.gpu.global.add.u32 [%0], 1;" :: "l"(g_flags + idx * 32) : "memory");
}
__device__ __forceinline__ void flag_wait(int idx, unsigned cnt, unsigned ep) {
  asm volatile("{\n.reg .pred p;\n.reg .u32 c, v;\n.reg .s32 d;\nmov.u32 c, 0;\nFLAG_LOOP:\n"
               "ld.acquire.gpu.global.u32 v, [%0];\nsub.s32 d, v, %1;\nsetp.ge.s32 p, d, 0;\n@p bra FLAG_DONE;\n"
               "add.u32 c, c, 1;\nsetp.lt.u32 p, c, %2;\n@p bra FLAG_LOOP;\ntrap;\nFLAG_DONE:\n}"
               :: "l"(g_flags + idx * 32), "r"((ep + 1) * cnt), "n"(WATCHDOG_SPINS) : "memory");
}
__device__ __forceinline__ uint4 lds16(uint32_t a) { uint4 v; asm volatile("ld.shared.v4.u32 {%0,%1,%2,%3}, [%4];" : "=r"(v.x), "=r"(v.y), "=r"(v.z), "=r"(v.w) : "r"(a) : "memory"); return v; }
__device__ __forceinline__ void sts16(uint32_t a, const uint4& v) { asm volatile("st.shared.v4.u32 [%0], {%1,%2,%3,%4};" :: "r"(a), "r"(v.x), "r"(v.y), "r"(v.z), "r"(v.w) : "memory"); }
__device__ __forceinline__ uint32_t ld4(const void* p) { uint32_t v; asm volatile("ld.global.ca.u32 %0, [%1];" : "=r"(v) : "l"(p)); return v; }

__device__ __forceinline__ void wgmma_ss_n64_tb0(float (&d)[32], uint64_t da, uint64_t db, int sd) {
  asm volatile("{\n.reg .pred p;\nsetp.ne.b32 p, %34, 0;\n"
    "wgmma.mma_async.sync.aligned.m64n64k16.f32.bf16.bf16 {%0, %1, %2, %3, %4, %5, %6, %7, %8, %9, %10, %11, %12, %13, %14, %15, %16, %17, %18, %19, %20, %21, %22, %23, %24, %25, %26, %27, %28, %29, %30, %31}, %32, %33, p, 1, 1, 0, 0;\n}\n"
    : "+f"(d[0]), "+f"(d[1]), "+f"(d[2]), "+f"(d[3]), "+f"(d[4]), "+f"(d[5]), "+f"(d[6]), "+f"(d[7]), "+f"(d[8]), "+f"(d[9]), "+f"(d[10]), "+f"(d[11]), "+f"(d[12]), "+f"(d[13]), "+f"(d[14]), "+f"(d[15]), "+f"(d[16]), "+f"(d[17]), "+f"(d[18]), "+f"(d[19]), "+f"(d[20]), "+f"(d[21]), "+f"(d[22]), "+f"(d[23]), "+f"(d[24]), "+f"(d[25]), "+f"(d[26]), "+f"(d[27]), "+f"(d[28]), "+f"(d[29]), "+f"(d[30]), "+f"(d[31])
    : "l"(da), "l"(db), "r"(sd));
}

__device__ __forceinline__ void wgmma_rs_n256_tb1(float (&d)[128], uint32_t a0, uint32_t a1, uint32_t a2, uint32_t a3, uint64_t db, int sd) {
  asm volatile("{\n.reg .pred p;\nsetp.ne.b32 p, %133, 0;\n"
    "wgmma.mma_async.sync.aligned.m64n256k16.f32.bf16.bf16 {%0, %1, %2, %3, %4, %5, %6, %7, %8, %9, %10, %11, %12, %13, %14, %15, %16, %17, %18, %19, %20, %21, %22, %23, %24, %25, %26, %27, %28, %29, %30, %31, %32, %33, %34, %35, %36, %37, %38, %39, %40, %41, %42, %43, %44, %45, %46, %47, %48, %49, %50, %51, %52, %53, %54, %55, %56, %57, %58, %59, %60, %61, %62, %63, %64, %65, %66, %67, %68, %69, %70, %71, %72, %73, %74, %75, %76, %77, %78, %79, %80, %81, %82, %83, %84, %85, %86, %87, %88, %89, %90, %91, %92, %93, %94, %95, %96, %97, %98, %99, %100, %101, %102, %103, %104, %105, %106, %107, %108, %109, %110, %111, %112, %113, %114, %115, %116, %117, %118, %119, %120, %121, %122, %123, %124, %125, %126, %127}, {%128, %129, %130, %131}, %132, p, 1, 1, 1;\n}\n"
    : "+f"(d[0]), "+f"(d[1]), "+f"(d[2]), "+f"(d[3]), "+f"(d[4]), "+f"(d[5]), "+f"(d[6]), "+f"(d[7]), "+f"(d[8]), "+f"(d[9]), "+f"(d[10]), "+f"(d[11]), "+f"(d[12]), "+f"(d[13]), "+f"(d[14]), "+f"(d[15]), "+f"(d[16]), "+f"(d[17]), "+f"(d[18]), "+f"(d[19]), "+f"(d[20]), "+f"(d[21]), "+f"(d[22]), "+f"(d[23]), "+f"(d[24]), "+f"(d[25]), "+f"(d[26]), "+f"(d[27]), "+f"(d[28]), "+f"(d[29]), "+f"(d[30]), "+f"(d[31]), "+f"(d[32]), "+f"(d[33]), "+f"(d[34]), "+f"(d[35]), "+f"(d[36]), "+f"(d[37]), "+f"(d[38]), "+f"(d[39]), "+f"(d[40]), "+f"(d[41]), "+f"(d[42]), "+f"(d[43]), "+f"(d[44]), "+f"(d[45]), "+f"(d[46]), "+f"(d[47]), "+f"(d[48]), "+f"(d[49]), "+f"(d[50]), "+f"(d[51]), "+f"(d[52]), "+f"(d[53]), "+f"(d[54]), "+f"(d[55]), "+f"(d[56]), "+f"(d[57]), "+f"(d[58]), "+f"(d[59]), "+f"(d[60]), "+f"(d[61]), "+f"(d[62]), "+f"(d[63]), "+f"(d[64]), "+f"(d[65]), "+f"(d[66]), "+f"(d[67]), "+f"(d[68]), "+f"(d[69]), "+f"(d[70]), "+f"(d[71]), "+f"(d[72]), "+f"(d[73]), "+f"(d[74]), "+f"(d[75]), "+f"(d[76]), "+f"(d[77]), "+f"(d[78]), "+f"(d[79]), "+f"(d[80]), "+f"(d[81]), "+f"(d[82]), "+f"(d[83]), "+f"(d[84]), "+f"(d[85]), "+f"(d[86]), "+f"(d[87]), "+f"(d[88]), "+f"(d[89]), "+f"(d[90]), "+f"(d[91]), "+f"(d[92]), "+f"(d[93]), "+f"(d[94]), "+f"(d[95]), "+f"(d[96]), "+f"(d[97]), "+f"(d[98]), "+f"(d[99]), "+f"(d[100]), "+f"(d[101]), "+f"(d[102]), "+f"(d[103]), "+f"(d[104]), "+f"(d[105]), "+f"(d[106]), "+f"(d[107]), "+f"(d[108]), "+f"(d[109]), "+f"(d[110]), "+f"(d[111]), "+f"(d[112]), "+f"(d[113]), "+f"(d[114]), "+f"(d[115]), "+f"(d[116]), "+f"(d[117]), "+f"(d[118]), "+f"(d[119]), "+f"(d[120]), "+f"(d[121]), "+f"(d[122]), "+f"(d[123]), "+f"(d[124]), "+f"(d[125]), "+f"(d[126]), "+f"(d[127])
    : "r"(a0), "r"(a1), "r"(a2), "r"(a3), "l"(db), "r"(sd));
}

__device__ __forceinline__ void wgmma_ss_n256_tb1(float (&d)[128], uint64_t da, uint64_t db, int sd) {
  asm volatile("{\n.reg .pred p;\nsetp.ne.b32 p, %130, 0;\n"
    "wgmma.mma_async.sync.aligned.m64n256k16.f32.bf16.bf16 {%0, %1, %2, %3, %4, %5, %6, %7, %8, %9, %10, %11, %12, %13, %14, %15, %16, %17, %18, %19, %20, %21, %22, %23, %24, %25, %26, %27, %28, %29, %30, %31, %32, %33, %34, %35, %36, %37, %38, %39, %40, %41, %42, %43, %44, %45, %46, %47, %48, %49, %50, %51, %52, %53, %54, %55, %56, %57, %58, %59, %60, %61, %62, %63, %64, %65, %66, %67, %68, %69, %70, %71, %72, %73, %74, %75, %76, %77, %78, %79, %80, %81, %82, %83, %84, %85, %86, %87, %88, %89, %90, %91, %92, %93, %94, %95, %96, %97, %98, %99, %100, %101, %102, %103, %104, %105, %106, %107, %108, %109, %110, %111, %112, %113, %114, %115, %116, %117, %118, %119, %120, %121, %122, %123, %124, %125, %126, %127}, %128, %129, p, 1, 1, 0, 1;\n}\n"
    : "+f"(d[0]), "+f"(d[1]), "+f"(d[2]), "+f"(d[3]), "+f"(d[4]), "+f"(d[5]), "+f"(d[6]), "+f"(d[7]), "+f"(d[8]), "+f"(d[9]), "+f"(d[10]), "+f"(d[11]), "+f"(d[12]), "+f"(d[13]), "+f"(d[14]), "+f"(d[15]), "+f"(d[16]), "+f"(d[17]), "+f"(d[18]), "+f"(d[19]), "+f"(d[20]), "+f"(d[21]), "+f"(d[22]), "+f"(d[23]), "+f"(d[24]), "+f"(d[25]), "+f"(d[26]), "+f"(d[27]), "+f"(d[28]), "+f"(d[29]), "+f"(d[30]), "+f"(d[31]), "+f"(d[32]), "+f"(d[33]), "+f"(d[34]), "+f"(d[35]), "+f"(d[36]), "+f"(d[37]), "+f"(d[38]), "+f"(d[39]), "+f"(d[40]), "+f"(d[41]), "+f"(d[42]), "+f"(d[43]), "+f"(d[44]), "+f"(d[45]), "+f"(d[46]), "+f"(d[47]), "+f"(d[48]), "+f"(d[49]), "+f"(d[50]), "+f"(d[51]), "+f"(d[52]), "+f"(d[53]), "+f"(d[54]), "+f"(d[55]), "+f"(d[56]), "+f"(d[57]), "+f"(d[58]), "+f"(d[59]), "+f"(d[60]), "+f"(d[61]), "+f"(d[62]), "+f"(d[63]), "+f"(d[64]), "+f"(d[65]), "+f"(d[66]), "+f"(d[67]), "+f"(d[68]), "+f"(d[69]), "+f"(d[70]), "+f"(d[71]), "+f"(d[72]), "+f"(d[73]), "+f"(d[74]), "+f"(d[75]), "+f"(d[76]), "+f"(d[77]), "+f"(d[78]), "+f"(d[79]), "+f"(d[80]), "+f"(d[81]), "+f"(d[82]), "+f"(d[83]), "+f"(d[84]), "+f"(d[85]), "+f"(d[86]), "+f"(d[87]), "+f"(d[88]), "+f"(d[89]), "+f"(d[90]), "+f"(d[91]), "+f"(d[92]), "+f"(d[93]), "+f"(d[94]), "+f"(d[95]), "+f"(d[96]), "+f"(d[97]), "+f"(d[98]), "+f"(d[99]), "+f"(d[100]), "+f"(d[101]), "+f"(d[102]), "+f"(d[103]), "+f"(d[104]), "+f"(d[105]), "+f"(d[106]), "+f"(d[107]), "+f"(d[108]), "+f"(d[109]), "+f"(d[110]), "+f"(d[111]), "+f"(d[112]), "+f"(d[113]), "+f"(d[114]), "+f"(d[115]), "+f"(d[116]), "+f"(d[117]), "+f"(d[118]), "+f"(d[119]), "+f"(d[120]), "+f"(d[121]), "+f"(d[122]), "+f"(d[123]), "+f"(d[124]), "+f"(d[125]), "+f"(d[126]), "+f"(d[127])
    : "l"(da), "l"(db), "r"(sd));
}

__device__ __forceinline__ void wgmma_rs_n64_tb1(float (&d)[32], uint32_t a0, uint32_t a1, uint32_t a2, uint32_t a3, uint64_t db, int sd) {
  asm volatile("{\n.reg .pred p;\nsetp.ne.b32 p, %37, 0;\n"
    "wgmma.mma_async.sync.aligned.m64n64k16.f32.bf16.bf16 {%0, %1, %2, %3, %4, %5, %6, %7, %8, %9, %10, %11, %12, %13, %14, %15, %16, %17, %18, %19, %20, %21, %22, %23, %24, %25, %26, %27, %28, %29, %30, %31}, {%32, %33, %34, %35}, %36, p, 1, 1, 1;\n}\n"
    : "+f"(d[0]), "+f"(d[1]), "+f"(d[2]), "+f"(d[3]), "+f"(d[4]), "+f"(d[5]), "+f"(d[6]), "+f"(d[7]), "+f"(d[8]), "+f"(d[9]), "+f"(d[10]), "+f"(d[11]), "+f"(d[12]), "+f"(d[13]), "+f"(d[14]), "+f"(d[15]), "+f"(d[16]), "+f"(d[17]), "+f"(d[18]), "+f"(d[19]), "+f"(d[20]), "+f"(d[21]), "+f"(d[22]), "+f"(d[23]), "+f"(d[24]), "+f"(d[25]), "+f"(d[26]), "+f"(d[27]), "+f"(d[28]), "+f"(d[29]), "+f"(d[30]), "+f"(d[31])
    : "r"(a0), "r"(a1), "r"(a2), "r"(a3), "l"(db), "r"(sd));
}


__global__ void __cluster_dims__(2, 1, 1) __launch_bounds__(384, 1)
fused_block_kernel(const __grid_constant__ Params p) {
  extern __shared__ __align__(1024) uint8_t smem[];
  const uint32_t sbase = smem_u32(smem);
  const int warp = threadIdx.x >> 5, lane = threadIdx.x & 31;
  const uint32_t rank = cluster_rank();
  const int cl = blockIdx.x >> 1;
  const int hp = cl >> 3;
  const int qt = ((cl & 7) << 1) + rank;
  const uint32_t bar_full = sbase + SM_BAR, bar_empty = sbase + SM_BAR + 40, bar_o1 = sbase + SM_BAR + 80, bar_x = sbase + SM_BAR + 88, bar_mod = sbase + SM_BAR + 96, bar_gv = sbase + SM_BAR + 104, bar_hold = sbase + SM_BAR + 112, bar_gvd = sbase + SM_BAR + 128;
  const uint32_t ring = sbase + SM_RING;

  unsigned ep0 = 0;
  if (warp == 9) ep0 = *reinterpret_cast<volatile unsigned*>(g_flags + FL_EPOCH * 32);
  if (threadIdx.x == 256) {
    mbar_init(bar_gv, 1);
    fence_async_smem();
    if (blockIdx.x < 112) {
      mbar_expect_tx(bar_gv, 7168 + 896);
      tma_load_2d(sbase + SM_GV, &p.tmWMu, bar_gv, blockIdx.x * 8, 0);
      tma_load_2d(sbase + SM_GV + 3584, &p.tmWMu, bar_gv, blockIdx.x * 8, 224);
      bulk_load(sbase + SM_GC, p.c, 896, bar_gv);
    }
    if ((sbase & 1023) != 0) asm volatile("trap;");
    for (int i = 0; i < NSLOT; i++) { mbar_init(bar_full + 8 * i, 1); mbar_init(bar_empty + 8 * i, 16); }
    mbar_init(bar_o1, 2);
    mbar_init(bar_x, 1);
    mbar_init(bar_mod, 1);
    mbar_init(bar_hold, 1);
    mbar_init(bar_gvd, 2);
    asm volatile("fence.mbarrier_init.release.cluster;" ::: "memory");
    fence_async_smem();
    mbar_expect_tx(bar_x, 65536);
    #pragma unroll 1
    for (int i = 0; i < 4; i++) tma_load_2d(sbase + SM_Q + i * 16384, &p.tmX, bar_x, 64 * i, qt * 128);
    mbar_expect_tx(bar_full, 32768);
    tma_load_2d(ring, &p.tmX, bar_full, 256, qt * 128); tma_load_2d(ring + 16384, &p.tmX, bar_full, 320, qt * 128);
    mbar_expect_tx(bar_full + 8, 16384);
    tma_load_2d(ring + SLOT, &p.tmX, bar_full + 8, 384, qt * 128);
  }
  __syncthreads();
  cluster_arrive();
  volatile unsigned* const sm_ep = reinterpret_cast<volatile unsigned*>(smem + SM_BAR + 120);

  if (warp >= 8) {
    asm volatile("setmaxnreg.dec.sync.aligned.u32 40;");
    if (warp == 8 && lane < NUM_MAPS) asm volatile("prefetch.tensormap [%0];" :: "l"(reinterpret_cast<const char*>(&p.tmK) + lane * 128) : "memory");
    __syncwarp();
    if (warp >= 9) {
      if (blockIdx.x < 112) {
        mbar_wait(bar_gv, 0);
        #pragma unroll 1
        for (int e = threadIdx.x - 288; e < 224; e += 96) {
          uint32_t cv;
          asm volatile("ld.shared.u32 %0, [%1];" : "=r"(cv) : "r"(sbase + SM_GC + e * 4) : "memory");
          cv = pack_bf16(silu_f(bf_lo(cv)), silu_f(bf_hi(cv)));
          asm volatile("st.shared.u32 [%0], %1;" :: "r"(sbase + SM_GC + e * 4), "r"(cv) : "memory");
        }
        named_sync(6, 96);
      }
      #pragma unroll 1
      for (int step = 0; step < 2; step++) {
        if (blockIdx.x < 112 && (step == 0) == (warp == 9)) {
          if (warp != 9) mbar_wait(bar_gv, 1);
          const uint32_t pitch = warp == 9 ? 16 : 32;
          const uint32_t wb = sbase + SM_GV + (warp == 11 ? 16 : 0) + lane * pitch, sv = sbase + SM_GC + (lane & 3) * 4;
          float d0[4] = {0.f, 0.f, 0.f, 0.f}, d1[4] = {0.f, 0.f, 0.f, 0.f};
          #pragma unroll 2
          for (int k = 0; k < 14; k++) {
            uint32_t b0, b1, b2, b3, a0, a1, a2, a3;
            asm volatile("ldmatrix.sync.aligned.m8n8.x4.trans.shared.b16 {%0, %1, %2, %3}, [%4];" : "=r"(b0), "=r"(b1), "=r"(b2), "=r"(b3) : "r"(wb + k * 32 * pitch) : "memory");
            asm volatile("ld.shared.u32 %0, [%1];" : "=r"(a0) : "r"(sv + k * 64) : "memory");
            asm volatile("ld.shared.u32 %0, [%1];" : "=r"(a1) : "r"(sv + k * 64 + 16) : "memory");
            asm volatile("ld.shared.u32 %0, [%1];" : "=r"(a2) : "r"(sv + k * 64 + 32) : "memory");
            asm volatile("ld.shared.u32 %0, [%1];" : "=r"(a3) : "r"(sv + k * 64 + 48) : "memory");
            mma16816(d0, a0, a0, a1, a1, b0, b1);
            mma16816(d1, a2, a2, a3, a3, b2, b3);
          }
          const uint32_t r2 = pack_bf16(d0[0] + d1[0], d0[1] + d1[1]);
          if (warp == 9) {
            uint32_t* d = g_modt + (lane >> 2) * (2 * DM) + blockIdx.x * 8 + (lane & 3) * 2;
            const uint32_t tg = (ep0 + 1) << 16;
            asm volatile("st.relaxed.gpu.global.v2.u32 [%0], {%1, %2};" :: "l"(d), "r"((r2 & 0xffffu) | tg), "r"((r2 >> 16) | tg) : "memory");
            __syncwarp();
            if (lane == 0) {
              mbar_arrive(bar_hold);
              fence_async_smem();
              mbar_expect_tx(bar_gv, 14336);
              tma_load_2d(sbase + SM_GV, &p.tmWMn, bar_gv, 2 * DM + blockIdx.x * 16, 0);
              tma_load_2d(sbase + SM_GV + 7168, &p.tmWMn, bar_gv, 2 * DM + blockIdx.x * 16, 224);
            }
          } else if (lane < 4) {
            reinterpret_cast<uint32_t*>(g_mod + 2 * DM + blockIdx.x * 16 + (warp - 10) * 8)[lane] = r2;
          }
          __syncwarp();
        }
        if (step == 1) break;
      {
        const unsigned epw = *reinterpret_cast<volatile unsigned*>(g_flags + FL_EPOCH * 32);
        const uint32_t tag = (epw + 1) & 0xffffu;
        const int e0 = threadIdx.x - 288;
        const uint32_t* src = g_modt + ((blockIdx.x >> 1) & 7) * (2 * DM) + e0 * 4;
        unsigned spins = 0;
        while (true) {
          uint4 m[3];
          bool ok = true;
          #pragma unroll
          for (int i = 0; i < 3; i++)
            asm volatile("ld.relaxed.gpu.global.v4.u32 {%0,%1,%2,%3}, [%4];" : "=r"(m[i].x), "=r"(m[i].y), "=r"(m[i].z), "=r"(m[i].w) : "l"(src + (i == 2 && e0 >= 32 ? 0 : i * 384)) : "memory");
          #pragma unroll
          for (int i = 0; i < 3; i++) {
            ok = ok && ((m[i].x >> 16) == tag) && ((m[i].y >> 16) == tag) && ((m[i].z >> 16) == tag) && ((m[i].w >> 16) == tag);
            const int e = e0 + 96 * i;
            uint32_t lo = (m[i].x & 0xffffu) | (m[i].y << 16), hi = (m[i].z & 0xffffu) | (m[i].w << 16);
            if (e >= 112) { lo = bf2_add(lo, 0x3F803F80u); hi = bf2_add(hi, 0x3F803F80u); }
            if (e < 224) *reinterpret_cast<uint2*>(smem + SM_MOD0 + e * 8) = make_uint2(lo, hi);
          }
          if (__all_sync(0xffffffffu, ok)) break;
          if (++spins > WATCHDOG_SPINS) asm volatile("trap;");
        }
        named_sync(6, 96);
        if (warp == 9 && lane == 0) { *sm_ep = ep0; mbar_arrive(bar_mod); }
        __syncwarp();
      }
      }
      if (warp >= 10) {
        if (lane == 0) mbar_arrive(bar_gvd);
        __syncwarp();
        const size_t off = (size_t)(qt * 128 + hp * 16) * DM;
        const uint4* src = reinterpret_cast<const uint4*>(p.x + off) + (warp - 10) * 32 + lane;
        uint4* dst = reinterpret_cast<uint4*>(p.out + off) + (warp - 10) * 32 + lane;
        #pragma unroll 1
        for (int h2 = 0; h2 < 2; h2++) {
          uint4 v[7];
          #pragma unroll
          for (int i = 0; i < 7; i++) v[i] = __ldg(src + (h2 * 7 + i) * 64);
          #pragma unroll
          for (int i = 0; i < 7; i++) dst[(h2 * 7 + i) * 64] = v[i];
        }
      }
      named_sync(7, 96);
      if (warp == 9) {
        if (lane == 0) {
          flag_signal(FL_MOD);
          flag_wait(FL_MOD, 128, ep0);
          mbar_wait(bar_o1, 0);
        }
        __syncwarp();
        #pragma unroll 1
        for (int e = lane; e < 112; e += 32) {
          const uint32_t* sc = reinterpret_cast<const uint32_t*>(g_mod + 4 * DM) + (e >> 2) * 8 + (e & 3);
          const uint32_t* sh = reinterpret_cast<const uint32_t*>(g_mod + 3 * DM) + (e >> 2) * 8 + (e & 3);
          uint4 m;
          m.x = bf2_add(ld4(sc), 0x3F803F80u); m.y = ld4(sh); m.z = bf2_add(ld4(sc + 4), 0x3F803F80u); m.w = ld4(sh + 4);
          *reinterpret_cast<uint4*>(smem + SM_MOD0 + e * 16) = m;
        }
        __syncwarp();
        if (lane == 0) mbar_arrive(bar_mod);
      }
    }
    __syncwarp();
    cluster_wait();
    if (warp == 8 && lane == 0) {
      uint32_t s = 0, pm = 0x1c;
      #define P_ACQ(bytes) do { mbar_wait(bar_empty + 8 * s, (pm >> s) & 1); pm ^= 1u << s; mbar_expect_tx(bar_full + 8 * s, (bytes)); } while (0)
      #define P_ADV() do { if (++s == NSLOT) s = 0; } while (0)
      s = 2;
      #pragma unroll 1
      for (int kc = 0; kc < 7; kc++) {
        if (kc == 3) {
          #pragma unroll 1
          for (int k2 = 3; k2 < 7; k2++) tma_prefetch_3d(&p.tmWQ, 0, k2 * 64, hp * 8 + rank * 2);
          #pragma unroll 1
          for (int j = 0; j < 2; j++) { tma_prefetch_3d(&p.tmK, 0, hp * 2 * SEQ + j * 64, rank * 2); tma_prefetch_3d(&p.tmV, 0, hp * 2 * SEQ + j * 64, rank * 2); }
        }
        P_ACQ(32768);
        tma_load_3d_mc(ring + s * SLOT + rank * 16384, &p.tmWQ, bar_full + 8 * s, 0, kc * 64, hp * 8 + rank * 2);
        if (++s == NSLOT) s = 2;
      }
      s = 0;
      const unsigned ep = *sm_ep;
      #pragma unroll 1
      for (int it = 0; it < 2; it++) {
        const int head = hp * 2 + it;
        if (it == 1) {
          flag_wait(FL_H + qt, 8, ep);
          fence_async_global();
          const uint32_t b0 = s;
          #pragma unroll 1
          for (int i = 0; i < 11; i++) {
            const int hs = i == 0 ? 0 : i == 3 ? 1 : i == 7 ? 2 : i == 9 ? 3 : -1;
            const int kc = i < 3 ? i - 1 : i < 7 ? i - 2 : i == 8 ? 5 : 6;
            const uint32_t rel = hs >= 0 ? ((hs & 1) ? 3u : 0u) : (kc % 3 == 0 ? 1u : kc % 3 == 1 ? 2u : 4u);
            s = b0 + rel; if (s >= NSLOT) s -= NSLOT;
            if (hs >= 0) {
              P_ACQ(hs < 3 ? 32768 : 16384);
              tma_load_2d(ring + s * SLOT, &p.tmH, bar_full + 8 * s, 128 * hs, qt * 128);
              if (hs < 3) tma_load_2d(ring + s * SLOT + 16384, &p.tmH, bar_full + 8 * s, 128 * hs + 64, qt * 128);
            } else {
              P_ACQ(32768);
              tma_load_3d_mc(ring + s * SLOT + rank * 16384, &p.tmWQ, bar_full + 8 * s, 0, kc * 64, head * 4 + rank * 2);
            }
          }
          s = b0 + 2; if (s >= NSLOT) s -= NSLOT;
        }
        #pragma unroll 1
        for (int j = 0; j < 64; j++) {
          if (j >= 8) {
            const int i = j - 8;
            if (it == 0) { if (i < 7) tma_prefetch_3d(&p.tmWQ, 0, i * 64, (head + 1) * 4 + rank * 2); }
            else if (i < 14) tma_prefetch_2d(&p.tmWO, (i >> 1) * 64, hp * 512 + (i & 1) * 256 + rank * 128);
            else if (i < 22) tma_prefetch_2d(&p.tmW1, hp * 224 + ((i - 14) >> 1) * 64, ((i - 14) & 1) * 224 + rank * 112);
            else if (i < 29) tma_prefetch_2d(&p.tmW2, (i - 22) * 64, hp * 224 + rank * 112);
          }
          P_ACQ(32768);
          tma_load_3d_mc(ring + s * SLOT + rank * 16384, (j & 1) ? &p.tmV : &p.tmK, bar_full + 8 * s, 0, head * SEQ + (j >> 1) * 64, rank * 2);
          P_ADV();
        }
      }
      mbar_wait(bar_o1, 0);
      fence_async_global();
      #pragma unroll 1
      for (int i = 0; i < 2; i++) {
        P_ACQ(32768);
        #pragma unroll 1
        for (int k = 0; k < 4; k++)
          tma_load_2d(ring + s * SLOT + k * 8192, &p.tmO1, bar_full + 8 * s, (2 * i + (k >> 1)) * 64, hp * SEQ + qt * 128 + (k & 1) * 64);
        P_ADV();
      }
      flag_wait(FL_MOD, 128, ep);
      #pragma unroll 1
      for (int i = 0; i < 14; i++) {
        P_ACQ(32768);
        tma_load_2d_mc(ring + s * SLOT + rank * 16384, &p.tmWO, bar_full + 8 * s, (i >> 1) * 64, hp * 512 + (i & 1) * 256 + rank * 128);
        P_ADV();
      }
      #pragma unroll 1
      for (int i = 0; i < 3; i++) {
        s = 2 + i;
        P_ACQ(28672);
        tma_load_2d_mc(ring + s * SLOT + rank * 14336, &p.tmW1, bar_full + 8 * s, hp * 224 + (i >> 1) * 64, (i & 1) * 224 + rank * 112);
      }
      mbar_wait(bar_o1, 1);
      flag_wait(FL_G1 + qt, 16, ep);
      fence_async_global();
      mbar_expect_tx(bar_x, 65536);
      #pragma unroll 1
      for (int i = 0; i < 4; i++) tma_load_2d(sbase + SM_Q + i * 16384, &p.tmX1, bar_x, 64 * i, qt * 128);
      s = 0; P_ACQ(32768);
      tma_load_2d(ring, &p.tmX1, bar_full, 256, qt * 128); tma_load_2d(ring + 16384, &p.tmX1, bar_full, 320, qt * 128);
      const uint32_t par0 = pm & 1;
      s = 1; P_ACQ(16384);
      tma_load_2d(ring + SLOT, &p.tmX1, bar_full + 8, 384, qt * 128);
      const uint32_t par1 = (pm >> 1) & 1;
      mbar_wait(bar_x, 1); mbar_wait(bar_full, par0); mbar_wait(bar_full + 8, par1);
      flag_signal_relaxed(FL_G2 + qt);
      s = 0;
      #pragma unroll 1
      for (int i = 3; i < 8; i++) {
        P_ACQ(28672);
        tma_load_2d_mc(ring + s * SLOT + rank * 14336, &p.tmW1, bar_full + 8 * s, hp * 224 + (i >> 1) * 64, (i & 1) * 224 + rank * 112);
        P_ADV();
      }
      flag_wait(FL_G2 + qt, 8, ep);
      #pragma unroll 1
      for (int i = 0; i < 7; i++) {
        P_ACQ(28672);
        tma_load_2d_mc(ring + s * SLOT + rank * 14336, &p.tmW2, bar_full + 8 * s, i * 64, hp * 224 + rank * 112);
        P_ADV();
      }
    }
  } else {
    asm volatile("setmaxnreg.inc.sync.aligned.u32 232;");
    const int wg = __shfl_sync(0xffffffffu, warp >> 2, 0), wq = warp & 3;
    const bool elected = (threadIdx.x & 127) == 0;

    {
      const bool has1 = lane < 24;
      const uint32_t rb = sbase + (uint32_t)(wg * 64 + wq * 16) * 128 + (lane >> 3) * 16384;
      uint4 nu[16], nw[16];
      if (blockIdx.x < 112) mbar_wait(bar_hold, 0);
      mbar_wait(bar_x, 0);
      mbar_wait(bar_full, 0); mbar_wait(bar_full + 8, 0);
      {
        uint32_t rstd2_lo, rstd2_hi, nb2_lo, nb2_hi;
        {
          const uint32_t lb = sbase + (uint32_t)(wg * 64 + wq * 16 + (lane & 7) + ((lane >> 3) & 1) * 8) * 128;
          const uint32_t sw = (uint32_t)(lane & 7), hi = (uint32_t)(lane >> 4);
          float d1[2][4], d2[2][4], d3[2][4];
          #pragma unroll
          for (int i = 0; i < 4; i++) { d1[0][i] = d1[1][i] = d2[0][i] = d2[1][i] = d3[0][i] = d3[1][i] = 0.f; }
          #pragma unroll 1
          for (int k = 0; k < 7; k++) {
            uint32_t a[4][4];
            #pragma unroll
            for (int ks = 0; ks < 4; ks++) ldsm_x4(a[ks][0], a[ks][1], a[ks][2], a[ks][3], lb + k * 16384 + (((2 * ks + hi) ^ sw) << 4));
            #pragma unroll
            for (int ks = 0; ks < 4; ks++) {
              mma16816(d1[ks & 1], a[ks][0], a[ks][1], a[ks][2], a[ks][3], 0x3F803F80u, 0x3F803F80u);
              mma16816(d2[ks & 1], a[ks][0], a[ks][1], a[ks][2], a[ks][3], a[ks][0], a[ks][2]);
              mma16816(d3[ks & 1], a[ks][0], a[ks][1], a[ks][2], a[ks][3], a[ks][1], a[ks][3]);
            }
          }
          const int g = lane >> 2;
          const int src = (g << 2) + (g >> 1);
          const float q0 = __shfl_sync(0xffffffffu, (g & 1) ? d2[0][1] + d2[1][1] : d2[0][0] + d2[1][0], src);
          const float q1 = __shfl_sync(0xffffffffu, (g & 1) ? d3[0][3] + d3[1][3] : d3[0][2] + d3[1][2], src);
          const float m0 = (d1[0][0] + d1[1][0]) * (1.0f / DM), m1 = (d1[0][2] + d1[1][2]) * (1.0f / DM);
          const float r0 = rsqrtf(fmaxf(q0 * (1.0f / DM) - m0 * m0, 0.f) + 1e-5f), r1 = rsqrtf(fmaxf(q1 * (1.0f / DM) - m1 * m1, 0.f) + 1e-5f);
          rstd2_lo = pack_bf16(r0, r0); rstd2_hi = pack_bf16(r1, r1);
          nb2_lo = pack_bf16(-m0 * r0, -m0 * r0); nb2_hi = pack_bf16(-m1 * r1, -m1 * r1);
        }
        #pragma unroll
        for (int r = 0; r < 16; r++) {
          const uint32_t a0 = rb + r * 128 + (((lane & 7) ^ (r & 7)) << 4);
          nu[r] = lds16(a0); nw[r] = lds16(has1 ? a0 + 65536 : a0);
        }
        #pragma unroll
        for (int r = 0; r < 16; r++) {
          const uint32_t nb2 = __shfl_sync(0xffffffffu, r < 8 ? nb2_lo : nb2_hi, (r & 7) << 2), rstd2 = __shfl_sync(0xffffffffu, r < 8 ? rstd2_lo : rstd2_hi, (r & 7) << 2);
          nu[r].x = bf2_fma(nu[r].x, rstd2, nb2); nu[r].y = bf2_fma(nu[r].y, rstd2, nb2); nu[r].z = bf2_fma(nu[r].z, rstd2, nb2); nu[r].w = bf2_fma(nu[r].w, rstd2, nb2);
          nw[r].x = bf2_fma(nw[r].x, rstd2, nb2); nw[r].y = bf2_fma(nw[r].y, rstd2, nb2); nw[r].z = bf2_fma(nw[r].z, rstd2, nb2); nw[r].w = bf2_fma(nw[r].w, rstd2, nb2);
        }
      }
      uint4 sh0 = make_uint4(0, 0, 0, 0), sh1 = sh0, sc0 = make_uint4(0x3F803F80u, 0x3F803F80u, 0x3F803F80u, 0x3F803F80u), sc1 = sc0;
      #pragma unroll 1
      for (int pass = __all_sync(0xffffffffu, mbar_test(bar_mod, 0)) ? 1 : 0; pass < 2; pass++) {
        if (pass == 1) {
          mbar_wait(bar_mod, 0);
          const uint32_t mb = sbase + SM_MOD0 + lane * 16;
          sh0 = lds16(mb); sc0 = lds16(mb + 896); sh1 = lds16(has1 ? mb + 512 : mb); sc1 = lds16(has1 ? mb + 896 + 512 : mb);
        }
        #pragma unroll
        for (int r = 0; r < 16; r++) {
          const uint32_t a0 = rb + r * 128 + (((lane & 7) ^ (r & 7)) << 4);
          nu[r].x = bf2_fma(nu[r].x, sc0.x, sh0.x); nu[r].y = bf2_fma(nu[r].y, sc0.y, sh0.y); nu[r].z = bf2_fma(nu[r].z, sc0.z, sh0.z); nu[r].w = bf2_fma(nu[r].w, sc0.w, sh0.w);
          nw[r].x = bf2_fma(nw[r].x, sc1.x, sh1.x); nw[r].y = bf2_fma(nw[r].y, sc1.y, sh1.y); nw[r].z = bf2_fma(nw[r].z, sc1.z, sh1.z); nw[r].w = bf2_fma(nw[r].w, sc1.w, sh1.w);
          if (pass == 1) { sts16(a0, nu[r]); if (has1) sts16(a0 + 65536, nw[r]); }
        }
      }
      fence_async_smem();
      named_sync(3 + wg, 128);
      if (elected && wg == (hp >> 2)) {
        #pragma unroll 1
        for (int k = 0; k < 7; k++) tma_store_2d(&p.tmH16, sbase + k * 16384 + hp * 2048, k * 64, qt * 128 + hp * 16);
        bulk_commit();
      }
      __syncwarp();
    }
    cluster_wait();

    uint32_t cs = 0, cm = 0;
    #define C_ADV() do { if (++cs == NSLOT) cs = 0; } while (0)
    #define C_WAIT() do { mbar_wait(bar_full + 8 * cs, (cm >> cs) & 1); cm ^= 1u << cs; } while (0)
    #define C_REL(slot) do { if (lane < 2) mbar_arrive_cluster(bar_empty + 8 * (slot), lane); __syncwarp(); } while (0)

    #define C_REL_DEP(slot, reg) do { const uint32_t z_ = (reg) & p.zero; \
        if (lane < 2) mbar_arrive_cluster(bar_empty + 8 * (slot) + z_, lane); __syncwarp(); } while (0)
    const int lrow = wq * 16 + (lane & 7) + ((lane >> 3) & 1) * 8;
    const uint32_t lsw = (uint32_t)(lane & 7);
    const uint32_t lhi = (uint32_t)(lane >> 4);
    const uint32_t a_row_off = (uint32_t)(wg * 64 + lrow) * 128;
    const uint32_t qreg = sbase + SM_Q;

    auto store_chunk = [&](const float (&acc)[32], const uint32_t (&g)[8], uint32_t piece) {
      const uint32_t b = piece + (uint32_t)lrow * 128;
      #pragma unroll
      for (int i = 0; i < 4; i++) {
        const float g0 = bf_lo(g[2*i]), g1 = bf_hi(g[2*i]), g2 = bf_lo(g[2*i+1]), g3 = bf_hi(g[2*i+1]);
        stsm_x4(b + (((2 * i + lhi) ^ lsw) << 4), pack_bf16(acc[8*i] * g0, acc[8*i+1] * g1), pack_bf16(acc[8*i+2] * g0, acc[8*i+3] * g1),
                pack_bf16(acc[8*i+4] * g2, acc[8*i+5] * g3), pack_bf16(acc[8*i+6] * g2, acc[8*i+7] * g3));
      }
    };
    auto load_gate = [&](uint32_t (&g)[8], const bf16* vec, int col0) {
      const uint32_t* q = reinterpret_cast<const uint32_t*>(vec + col0) + (lane & 3);
      #pragma unroll
      for (int i = 0; i < 8; i++) g[i] = ld4(q + 4 * i);
    };

    #define PP_WAIT() named_sync(1 + wg, 256)
    #define PP_DONE() named_arrive(1 + (wg ^ 1), 256)
    float o[128];
    float inv0 = 0.f, inv1 = 0.f;
    if (wg == 0) named_arrive(1, 256);

    #pragma unroll 1
    for (int it = 0; it < 2; it++) {
      {
        uint32_t sh = 0;
        if (it == 0) { cm = 3; cs = 2; }
        const uint32_t b0 = cs;
        #pragma unroll 1
        for (int kc = 0; kc < 7; kc++) {
          uint32_t aaddr;
          if (it == 0) {
            aaddr = qreg + kc * 16384;
          } else {
            if ((kc & 1) == 0) { sh = b0 + ((kc & 2) ? 3 : 0); if (sh >= NSLOT) sh -= NSLOT; cs = sh; C_WAIT(); }
            aaddr = ring + sh * SLOT + (kc & 1) * 16384;
            cs = b0 + (kc % 3 == 0 ? 1 : kc % 3 == 1 ? 2 : 4); if (cs >= NSLOT) cs -= NSLOT;
          }
          C_WAIT(); const uint32_t sb = cs;
          if (it == 0 && ++cs == NSLOT) cs = 2;
          const uint32_t ab = desc_lo(aaddr + wg * 8192, 16), bb = desc_lo(ring + sb * SLOT, 8192);
          PP_WAIT();
          wg_fence();
          #pragma unroll
          for (int ks = 0; ks < 4; ks++)
            wgmma_ss_n256_tb1(o, mk_desc(ab + ks * 2, HI_SW128), mk_desc(bb + ks * 128, HI_SW128), (kc | ks) != 0);
          wg_commit();
          PP_DONE();
          if (kc == 4) { if (elected) bulk_wait_read<0>(); __syncwarp(); }
          wg_wait<0>();
          C_REL(sb);
          if (it == 1 && ((kc & 1) == 1 || kc == 6)) C_REL(sh);
          if (it == 0 && kc == 6) mbar_wait(bar_gvd, 0);
          if (it == 0 && kc >= 5) C_REL(kc - 5);
        }
        reg_fence(o);
        if (it == 0) cs = 0; else { cs = b0 + 2; if (cs >= NSLOT) cs -= NSLOT; }
        named_sync(3 + wg, 128);
        #pragma unroll
        for (int c = 0; c < 4; c++) {
          const uint32_t b = qreg + c * 16384 + wg * 8192 + (uint32_t)lrow * 128;
          #pragma unroll
          for (int i = 0; i < 4; i++) {
            const int g = 32 * c + 8 * i;
            stsm_x4(b + (((2 * i + lhi) ^ lsw) << 4), pack_bf16(o[g], o[g+1]), pack_bf16(o[g+2], o[g+3]), pack_bf16(o[g+4], o[g+5]), pack_bf16(o[g+6], o[g+7]));
          }
        }
        fence_async_smem();
        named_sync(3 + wg, 128);
      }
      {
        constexpr float c = 0.0625f * 1.4426950408889634f;
        float s[32];
        uint32_t pr[16];
        float m0 = -INFINITY, m1 = -INFINITY, l0 = 0.f, l1 = 0.f;
        uint32_t sK, sV;
        const uint32_t qdesc = desc_lo(qreg + wg * 8192, 16);
        uint32_t kb, vb;
        auto wait_k = [&]() { C_WAIT(); sK = cs; C_ADV(); kb = desc_lo(ring + sK * SLOT, 16); };
        auto wait_v = [&]() { C_WAIT(); sV = cs; C_ADV(); vb = desc_lo(ring + sV * SLOT, 8192); };
        auto issue_qk = [&]() {
          wg_fence();
          #pragma unroll
          for (int i = 0; i < 16; i++)
            wgmma_ss_n64_tb0(s, mk_desc(qdesc + (i >> 2) * 1024 + (i & 3) * 2, HI_SW128), mk_desc(kb + (i >> 2) * 512 + (i & 3) * 2, HI_SW128), i > 0);
          wg_commit();
        };
        auto issue_pv = [&](int first) {
          wg_fence();
          #pragma unroll
          for (int i = 0; i < 4; i++)
            wgmma_rs_n256_tb1(o, pr[4*i], pr[4*i+1], pr[4*i+2], pr[4*i+3], mk_desc(vb + i * 128, HI_SW128), i > 0 || !first);
          wg_commit();
        };
        auto softmax = [&](int first) {
          float mc0 = m0 * c, mc1 = m1 * c;
          float r0 = 0.f, r1 = 0.f, r2 = 0.f, r3 = 0.f;
          #pragma unroll
          for (int i = 0; i < 8; i++) {
            float e0 = ex2(fmaf(s[4*i], c, -mc0)), e1 = ex2(fmaf(s[4*i+1], c, -mc0));
            float e2 = ex2(fmaf(s[4*i+2], c, -mc1)), e3 = ex2(fmaf(s[4*i+3], c, -mc1));
            r0 += e0; r2 += e1; r1 += e2; r3 += e3;
            pr[2*i] = pack_bf16(e0, e1); pr[2*i+1] = pack_bf16(e2, e3);
          }
          r0 += r2; r1 += r3;
          if (__any_sync(0xffffffffu, !(r0 <= 256.f) | !(r1 <= 256.f))) {
            float x0 = s[0], x1 = s[2];
            #pragma unroll
            for (int i = 0; i < 8; i++) { x0 = fmaxf(x0, fmaxf(s[4*i], s[4*i+1])); x1 = fmaxf(x1, fmaxf(s[4*i+2], s[4*i+3])); }
            x0 = fmaxf(x0, __shfl_xor_sync(0xffffffffu, x0, 1)); x1 = fmaxf(x1, __shfl_xor_sync(0xffffffffu, x1, 1));
            x0 = fmaxf(x0, __shfl_xor_sync(0xffffffffu, x0, 2)); x1 = fmaxf(x1, __shfl_xor_sync(0xffffffffu, x1, 2));
            const float mn0 = fmaxf(m0, x0), mn1 = fmaxf(m1, x1);
            const float b0 = ex2((m0 - mn0) * c), b1 = ex2((m1 - mn1) * c);
            m0 = mn0; m1 = mn1; mc0 = mn0 * c; mc1 = mn1 * c;
            l0 *= b0; l1 *= b1;
            if (!first) {
              #pragma unroll
              for (int i = 0; i < 32; i++) { o[4*i] *= b0; o[4*i+1] *= b0; o[4*i+2] *= b1; o[4*i+3] *= b1; }
            }
            r0 = r1 = r2 = r3 = 0.f;
            #pragma unroll
            for (int i = 0; i < 8; i++) {
              float e0 = ex2(fmaf(s[4*i], c, -mc0)), e1 = ex2(fmaf(s[4*i+1], c, -mc0));
              float e2 = ex2(fmaf(s[4*i+2], c, -mc1)), e3 = ex2(fmaf(s[4*i+3], c, -mc1));
              r0 += e0; r2 += e1; r1 += e2; r3 += e3;
              pr[2*i] = pack_bf16(e0, e1); pr[2*i+1] = pack_bf16(e2, e3);
            }
            r0 += r2; r1 += r3;
          }
          l0 += r0; l1 += r1;
        };
        wait_k();
        PP_WAIT();
        issue_qk();
        PP_DONE();
        if (it == 1 && elected) { bulk_wait<0>(); mbar_arrive(bar_o1); }
        if (it == 0 && elected && wg == (hp >> 2)) { bulk_wait<0>(); flag_signal_relaxed(FL_H + qt); }
        __syncwarp();
        wg_wait<0>(); reg_fence(s); C_REL(sK);
        #pragma unroll 1
        for (int j = 0; j < 32; j++) {
          softmax(j == 0);
          wait_v();
          if (j < 31) wait_k();
          PP_WAIT();
          issue_pv(j == 0);
          if (j < 31) issue_qk(); else wg_commit();
          PP_DONE();
          wg_wait<1>(); C_REL(sV);
          wg_wait<0>(); reg_fence(s); reg_fence(o);
          if (j < 31) C_REL(sK);
        }
        l0 += __shfl_xor_sync(0xffffffffu, l0, 1); l0 += __shfl_xor_sync(0xffffffffu, l0, 2);
        l1 += __shfl_xor_sync(0xffffffffu, l1, 1); l1 += __shfl_xor_sync(0xffffffffu, l1, 2);
        inv0 = 1.f / l0; inv1 = 1.f / l1;
      }
      if (it == 0) {
        #pragma unroll
        for (int c = 0; c < 4; c++) {
          const uint32_t b = qreg + c * 16384 + wg * 8192 + (uint32_t)lrow * 128;
          #pragma unroll
          for (int i = 0; i < 4; i++) {
            const int g = 32 * c + 8 * i;
            stsm_x4(b + (((2 * i + lhi) ^ lsw) << 4), pack_bf16(o[g] * inv0, o[g+1] * inv0), pack_bf16(o[g+2] * inv1, o[g+3] * inv1),
                    pack_bf16(o[g+4] * inv0, o[g+5] * inv0), pack_bf16(o[g+6] * inv1, o[g+7] * inv1));
          }
        }
        fence_async_smem();
        named_sync(3 + wg, 128);
        if (elected) {
          #pragma unroll 1
          for (int c = 0; c < 4; c++) tma_store_2d(&p.tmO1, qreg + c * 16384 + wg * 8192, c * 64, hp * SEQ + qt * 128 + wg * 64);
          bulk_commit();
        }
        __syncwarp();
      }
    }

    {
      uint32_t a2[64], a1[64];
      #pragma unroll
      for (int k = 0; k < 16; k++) {
        a2[4*k]   = pack_bf16(o[8*k] * inv0, o[8*k+1] * inv0);   a2[4*k+1] = pack_bf16(o[8*k+2] * inv1, o[8*k+3] * inv1);
        a2[4*k+2] = pack_bf16(o[8*k+4] * inv0, o[8*k+5] * inv0); a2[4*k+3] = pack_bf16(o[8*k+6] * inv1, o[8*k+7] * inv1);
      }
      #pragma unroll
      for (int sl = 0; sl < 2; sl++) {
        C_WAIT();
        const uint32_t b = ring + cs * SLOT + a_row_off;
        #pragma unroll
        for (int j = 0; j < 2; j++) {
          #pragma unroll
          for (int ks = 0; ks < 4; ks++) {
            const int k = (2 * sl + j) * 4 + ks;
            ldsm_x4(a1[4*k], a1[4*k+1], a1[4*k+2], a1[4*k+3], b + j * 16384 + (((2 * ks + lhi) ^ lsw) << 4));
          }
        }
        uint32_t dep = 0;
        #pragma unroll
        for (int kk = 0; kk < 8; kk++) dep |= a1[4 * (8 * sl + kk)];
        C_REL_DEP(cs, dep); C_ADV();
      }
      if (elected) fence_async_global();
      float acc[32];
      #pragma unroll 1
      for (int c = 0; c < 7; c++) {
        uint32_t gt[8];
        load_gate(gt, g_mod + 2 * DM, c * 64);
        C_WAIT(); const uint32_t s0 = cs; C_ADV();
        C_WAIT(); const uint32_t s1 = cs; C_ADV();
        const uint32_t d0 = desc_lo(ring + s0 * SLOT, 16), d1 = desc_lo(ring + s1 * SLOT, 16);
        PP_WAIT();
        wg_fence();
        #pragma unroll
        for (int ks = 0; ks < 16; ks++)
          wgmma_rs_n64_tb1(acc, a1[4*ks], a1[4*ks+1], a1[4*ks+2], a1[4*ks+3], mk_desc(d0 + ks * 128, HI_SW128), ks > 0);
        wg_commit();
        #pragma unroll
        for (int ks = 0; ks < 16; ks++)
          wgmma_rs_n64_tb1(acc, a2[4*ks], a2[4*ks+1], a2[4*ks+2], a2[4*ks+3], mk_desc(d1 + ks * 128, HI_SW128), 1);
        wg_commit();
        PP_DONE();
        if (elected) {
          if (c > 0) { tma_reduce_add_2d(&p.tmOut, qreg + ((c - 1) & 3) * 16384 + wg * 8192, (c - 1) * 64, qt * 128 + wg * 64); bulk_commit(); }
          bulk_wait_read<3>();
        }
        __syncwarp();
        wg_wait<1>(); C_REL(s0);
        named_sync(3 + wg, 128);
        wg_wait<0>(); reg_fence(acc); C_REL(s1);
        store_chunk(acc, gt, qreg + (c & 3) * 16384 + wg * 8192);
        fence_async_smem();
        named_sync(3 + wg, 128);
      }
      if (elected) { tma_reduce_add_2d(&p.tmOut, qreg + (6 & 3) * 16384 + wg * 8192, 6 * 64, qt * 128 + wg * 64); bulk_commit(); }
      if (elected) { bulk_wait<0>(); mbar_arrive(bar_o1); flag_signal_relaxed(FL_G1 + qt); }
      __syncwarp();
    }

    {
      {
        uint32_t af[112];
        #pragma unroll 1
        for (int pass = 0; pass < 2; pass++) {
          if (pass == 1) { mbar_wait(bar_mod, 1); mbar_wait(bar_x, 1); }
          float d1[2][4], d2[2][4], d3[2][4];
          #pragma unroll
          for (int i = 0; i < 4; i++) { d1[0][i] = d1[1][i] = d2[0][i] = d2[1][i] = d3[0][i] = d3[1][i] = 0.f; }
          #pragma unroll
          for (int k4 = 0; k4 < 7; k4++) {
            if (k4 == 4 && pass == 1) { cs = 0; C_WAIT(); }
            if (k4 == 6 && pass == 1) { cs = 1; C_WAIT(); }
            #pragma unroll
            for (int k = 4 * k4; k < 4 * k4 + 4; k++)
              ldsm_x4(af[4*k], af[4*k+1], af[4*k+2], af[4*k+3], sbase + k4 * 16384 + a_row_off + (((2 * (k & 3) + lhi) ^ lsw) << 4));
            #pragma unroll
            for (int k = 4 * k4; k < 4 * k4 + 4; k++) {
              mma16816(d1[k & 1], af[4*k], af[4*k+1], af[4*k+2], af[4*k+3], 0x3F803F80u, 0x3F803F80u);
              mma16816(d2[k & 1], af[4*k], af[4*k+1], af[4*k+2], af[4*k+3], af[4*k], af[4*k+2]);
              mma16816(d3[k & 1], af[4*k], af[4*k+1], af[4*k+2], af[4*k+3], af[4*k+1], af[4*k+3]);
            }
          }
          if (pass == 1) {
            C_REL_DEP(0, __float_as_uint(d2[0][0] + d2[1][0])); C_REL_DEP(1, __float_as_uint(d2[0][0] + d2[1][0]));
            cs = 2;
          }
          const int g = lane >> 2;
          const int src = (g << 2) + (g >> 1);
          const float q0 = __shfl_sync(0xffffffffu, (g & 1) ? d2[0][1] + d2[1][1] : d2[0][0] + d2[1][0], src);
          const float q1 = __shfl_sync(0xffffffffu, (g & 1) ? d3[0][3] + d3[1][3] : d3[0][2] + d3[1][2], src);
          const float m0 = (d1[0][0] + d1[1][0]) * (1.0f / DM), m1 = (d1[0][2] + d1[1][2]) * (1.0f / DM);
          const float r0 = rsqrtf(fmaxf(q0 * (1.0f / DM) - m0 * m0, 0.f) + 1e-5f), r1 = rsqrtf(fmaxf(q1 * (1.0f / DM) - m1 * m1, 0.f) + 1e-5f);
          const uint32_t rs0 = pack_bf16(r0, r0), rs1 = pack_bf16(r1, r1), nb0 = pack_bf16(-m0 * r0, -m0 * r0), nb1 = pack_bf16(-m1 * r1, -m1 * r1);
          const uint32_t mb = sbase + SM_MOD0 + (lane & 3) * 16;
          #pragma unroll
          for (int k = 0; k < 28; k++) {
            const uint4 m = lds16(mb + k * 64);
            af[4*k]   = bf2_fma(bf2_fma(af[4*k],   rs0, nb0), m.x, m.y);
            af[4*k+1] = bf2_fma(bf2_fma(af[4*k+1], rs1, nb1), m.x, m.y);
            af[4*k+2] = bf2_fma(bf2_fma(af[4*k+2], rs0, nb0), m.z, m.w);
            af[4*k+3] = bf2_fma(bf2_fma(af[4*k+3], rs1, nb1), m.z, m.w);
          }
        }
        named_sync(3 + wg, 128);
        #pragma unroll 1
        for (int c = 0; c < 4; c++) {
          float acc[32];
          C_WAIT(); const uint32_t s0 = cs; C_ADV();
          C_WAIT(); const uint32_t s1 = cs; C_ADV();
          const uint32_t d0 = desc_lo(ring + s0 * SLOT, 16), d1 = desc_lo(ring + s1 * SLOT, 16);
          PP_WAIT();
          wg_fence();
          #pragma unroll
          for (int ks = 0; ks < 14; ks++)
            wgmma_rs_n64_tb1(acc, af[4*ks], af[4*ks+1], af[4*ks+2], af[4*ks+3], mk_desc(d0 + ks * 128, HI_SW128), ks > 0);
          wg_commit();
          #pragma unroll
          for (int ks = 0; ks < 14; ks++)
            wgmma_rs_n64_tb1(acc, af[56+4*ks], af[56+4*ks+1], af[56+4*ks+2], af[56+4*ks+3], mk_desc(d1 + ks * 128, HI_SW128), 1);
          wg_commit();
          PP_DONE();
          wg_wait<1>(); C_REL(s0);
          wg_wait<0>(); reg_fence(acc); C_REL(s1);
          const uint32_t b = qreg + c * 16384 + wg * 8192 + (uint32_t)lrow * 128;
          uint32_t hp_[16];
          #pragma unroll
          for (int i = 0; i < 16; i++) hp_[i] = silu2_pack(acc[2*i], acc[2*i+1]);
          #pragma unroll
          for (int i = 0; i < 4; i++) stsm_x4(b + (((2 * i + lhi) ^ lsw) << 4), hp_[4*i], hp_[4*i+1], hp_[4*i+2], hp_[4*i+3]);
        }
      }
      __syncwarp();
      uint32_t hf[56];
      #pragma unroll
      for (int k = 0; k < 14; k++)
        ldsm_x4(hf[4*k], hf[4*k+1], hf[4*k+2], hf[4*k+3], qreg + (k >> 2) * 16384 + wg * 8192 + (uint32_t)lrow * 128 + (((2 * (k & 3) + lhi) ^ lsw) << 4));
      named_sync(3 + wg, 128);
      #pragma unroll 1
      for (int c = 0; c < 7; c++) {
        float acc[32];
        uint32_t gt[8];
        load_gate(gt, g_mod + 5 * DM, c * 64);
        C_WAIT(); const uint32_t s0 = cs; C_ADV();
        const uint32_t d0 = desc_lo(ring + s0 * SLOT, 16);
        PP_WAIT();
        wg_fence();
        #pragma unroll
        for (int ks = 0; ks < 14; ks++)
          wgmma_rs_n64_tb1(acc, hf[4*ks], hf[4*ks+1], hf[4*ks+2], hf[4*ks+3], mk_desc(d0 + ks * 128, HI_SW128), ks > 0);
        wg_commit();
        if (!(c == 6 && wg == 1)) PP_DONE();
        if (elected) bulk_wait_read<3>();
        __syncwarp();
        named_sync(3 + wg, 128);
        wg_wait<0>(); reg_fence(acc);
        if (c < 2) C_REL(s0);
        const uint32_t piece = qreg + (c & 3) * 16384 + wg * 8192;
        store_chunk(acc, gt, piece);
        fence_async_smem();
        named_sync(3 + wg, 128);
        if (elected) { tma_reduce_add_2d(&p.tmOut, piece, c * 64, qt * 128 + wg * 64); bulk_commit(); }
        __syncwarp();
      }
      if (elected) bulk_wait<0>();
      __syncwarp();
    }
  }
  if (threadIdx.x == 0 && blockIdx.x == 0) g_flags[FL_EPOCH * 32] = *sm_ep + 1;
}

typedef CUresult (*EncodeFn)(CUtensorMap*, CUtensorMapDataType, cuuint32_t, void*, const cuuint64_t*, const cuuint64_t*,
                             const cuuint32_t*, const cuuint32_t*, CUtensorMapInterleave, CUtensorMapSwizzle,
                             CUtensorMapL2promotion, CUtensorMapFloatOOBfill);

void enc2d(EncodeFn enc, CUtensorMap* tm, const void* base, uint64_t cols, uint64_t rows, uint32_t bc, uint32_t br, CUtensorMapSwizzle sw) {
  cuuint64_t dims[2] = {cols, rows}; cuuint64_t strides[1] = {cols * 2}; cuuint32_t box[2] = {bc, br}; cuuint32_t es[2] = {1, 1};
  enc(tm, CU_TENSOR_MAP_DATA_TYPE_BFLOAT16, 2, const_cast<void*>(base), dims, strides, box, es, CU_TENSOR_MAP_INTERLEAVE_NONE, sw,
      CU_TENSOR_MAP_L2_PROMOTION_L2_128B, CU_TENSOR_MAP_FLOAT_OOB_FILL_NONE);
}
void enc_kv(EncodeFn enc, CUtensorMap* tm, const void* base) {
  cuuint64_t dims[3] = {64, (cuuint64_t)NH * SEQ, 4}; cuuint64_t strides[2] = {512, 128}; cuuint32_t box[3] = {64, 64, 2}; cuuint32_t es[3] = {1, 1, 1};
  enc(tm, CU_TENSOR_MAP_DATA_TYPE_BFLOAT16, 3, const_cast<void*>(base), dims, strides, box, es, CU_TENSOR_MAP_INTERLEAVE_NONE,
      CU_TENSOR_MAP_SWIZZLE_128B, CU_TENSOR_MAP_L2_PROMOTION_L2_128B, CU_TENSOR_MAP_FLOAT_OOB_FILL_NONE);
}

}

extern "C" void kernel_launch(void* const* d_in, const int* in_sizes, int n_in, void* d_out, int out_size) {
  (void)in_sizes; (void)n_in; (void)out_size;
  static EncodeFn enc = nullptr;
  static void *ph, *po1;
  if (!enc) {
    void* fn = nullptr; cudaDriverEntryPointQueryResult qr;
    cudaGetDriverEntryPoint("cuTensorMapEncodeTiled", &fn, cudaEnableDefault, &qr);
    enc = (EncodeFn)fn;
    cudaGetSymbolAddress(&ph, g_h); cudaGetSymbolAddress(&po1, g_o1);
    cudaFuncSetAttribute(fused_block_kernel, cudaFuncAttributeMaxDynamicSharedMemorySize, SM_LAUNCH);
  }
  Params prm;
  enc_kv(enc, &prm.tmK, d_in[1]);
  enc_kv(enc, &prm.tmV, d_in[2]);
  {
    cuuint64_t dims[3] = {64, DM, (cuuint64_t)NH * 4}; cuuint64_t strides[2] = {NH * HD * 2, 128}; cuuint32_t box[3] = {64, 64, 2}; cuuint32_t es[3] = {1, 1, 1};
    enc(&prm.tmWQ, CU_TENSOR_MAP_DATA_TYPE_BFLOAT16, 3, d_in[3], dims, strides, box, es, CU_TENSOR_MAP_INTERLEAVE_NONE,
        CU_TENSOR_MAP_SWIZZLE_128B, CU_TENSOR_MAP_L2_PROMOTION_L2_128B, CU_TENSOR_MAP_FLOAT_OOB_FILL_NONE);
  }
  enc2d(enc, &prm.tmH, ph, DM, SEQ, 64, 128, CU_TENSOR_MAP_SWIZZLE_128B);
  enc2d(enc, &prm.tmH16, ph, DM, SEQ, 64, 16, CU_TENSOR_MAP_SWIZZLE_128B);
  enc2d(enc, &prm.tmO1, po1, HD, 8 * SEQ, 64, 64, CU_TENSOR_MAP_SWIZZLE_128B);
  enc2d(enc, &prm.tmWO, d_in[4], DM, NH * HD, 64, 128, CU_TENSOR_MAP_SWIZZLE_128B);
  enc2d(enc, &prm.tmOut, d_out, DM, SEQ, 64, 64, CU_TENSOR_MAP_SWIZZLE_128B);
  enc2d(enc, &prm.tmX1, d_out, DM, SEQ, 64, 128, CU_TENSOR_MAP_SWIZZLE_128B);
  enc2d(enc, &prm.tmW1, d_in[6], FF, DM, 64, 112, CU_TENSOR_MAP_SWIZZLE_128B);
  enc2d(enc, &prm.tmX, d_in[0], DM, SEQ, 64, 128, CU_TENSOR_MAP_SWIZZLE_128B);
  enc2d(enc, &prm.tmWMu, d_in[9], 6 * DM, DM, 8, 224, CU_TENSOR_MAP_SWIZZLE_NONE);
  enc2d(enc, &prm.tmWMn, d_in[9], 6 * DM, DM, 16, 224, CU_TENSOR_MAP_SWIZZLE_NONE);
  enc2d(enc, &prm.tmW2, d_in[7], DM, FF, 64, 112, CU_TENSOR_MAP_SWIZZLE_128B);
  prm.x = (const bf16*)d_in[0]; prm.c = (const bf16*)d_in[8]; prm.wmod = (const bf16*)d_in[9]; prm.out = (bf16*)d_out; prm.zero = 0;
  fused_block_kernel<<<128, 384, SM_LAUNCH, cudaStreamPerThread>>>(prm);
}
```
